```python
import torch

def _softmax(x, axis=-1):
    return torch.softmax(x, dim=axis)

def _gelu(x):
    return torch.nn.functional.gelu(x, approximate='tanh')

def _silu(x):
    return torch.nn.functional.silu(x)

def _sigmoid(x):
    return torch.sigmoid(x)

def _layernorm(x, axis=-1, eps=1e-05):
    m = x.mean(dim=axis, keepdim=True)
    v = x.var(dim=axis, keepdim=True, unbiased=False)
    return (x - m) / torch.sqrt(v + eps)

def _scatter_add(tgt, idx, src, axis=0):
    return tgt.clone().index_add_(axis, idx, src)

def _segment_sum(src, seg, n):
    out = torch.zeros((n,) + src.shape[1:], dtype=src.dtype)
    return out.index_add_(0, seg, src)

def _pad(x, pw):
    flat = tuple((v for pair in reversed(pw) for v in pair))
    return torch.nn.functional.pad(x, flat)
kernel_name = 'gather_scatter__tensor_product_equiv_equiformer__graph'

def setup_inputs():

    _w = lambda a: (lambda t: t.to(torch.bfloat16) if t.is_floating_point() else t)(torch.as_tensor(a))
    N, deg, C, De = (25000, 32, 64, max(0, 1))
    E = N * deg
    src = (lambda lo, hi, *s: torch.randint(lo, hi, s))(0, N, E).to(torch.int64)
    dst = (lambda lo, hi, *s: torch.randint(lo, hi, s))(0, N, E).to(torch.int64)
    rvec = (lambda *s: torch.randn(*s, dtype=torch.bfloat16) * 0.05)(E, 3).to(float)
    rn = (torch.linalg.norm(rvec, dim=-1, keepdim=True) + 1e-06).to(float)
    rhat = (rvec / rn).to(float)
    eps = torch.zeros((3, 3, 3), dtype=float)
    eps[0, 1, 2] = eps[1, 2, 0] = eps[2, 0, 1] = 1.0
    eps[0, 2, 1] = eps[2, 1, 0] = eps[1, 0, 2] = -1.0
    return {'x': _w((lambda *s: torch.randn(*s, dtype=torch.bfloat16) * 0.4)(N, 4 * C).to(float)), 'rhat': _w(rhat), 'e_attr': _w((lambda *s: torch.randn(*s, dtype=torch.bfloat16) * 0.4)(E, De).to(float)), 'src': _w(src), 'dst': _w(dst), 'w_rad': _w((lambda *s: torch.randn(*s, dtype=torch.bfloat16) * 0.4)(De, 5 * C).to(float)), 'w_si0': _w((lambda *s: torch.randn(*s, dtype=torch.bfloat16) * 0.4)(2 * C, C).to(float)), 'w_si1': _w((lambda *s: torch.randn(*s, dtype=torch.bfloat16) * 0.05)(3 * C, C).to(float)), 'cg_eps': _w(eps)}

def reference(x, rhat, e_attr, src, dst, w_rad, w_si0, w_si1, cg_eps):
    N = x.shape[0]
    C = w_si0.shape[1]
    E = rhat.shape[0]
    x0 = x[:, :C].clone()
    x1 = x[:, C:].reshape(N, 3, C)
    R = (e_attr @ w_rad).reshape(E, 5, C)
    f0 = x0[src]
    f1 = x1[src]
    Y1 = rhat
    p00_0 = f0 * R[:, 0, :]
    p11_0 = torch.einsum('ejc,ej->ec', f1, Y1) * R[:, 1, :]
    p01_1 = torch.einsum('ec,ej->ejc', f0, Y1) * R[:, 2, :][:, None, :]
    p10_1 = f1 * R[:, 3, :][:, None, :]
    p11_1 = torch.einsum('ijk,ekc,ej->eic', cg_eps, f1, Y1) * R[:, 4, :][:, None, :]
    m0 = torch.concatenate([p00_0, p11_0], axis=-1) @ w_si0
    m1 = torch.einsum('ejp,pc->ejc', torch.concatenate([p01_1, p10_1, p11_1], axis=-1), w_si1)
    agg0 = _segment_sum(m0, dst, N)
    agg1 = _segment_sum(m1.reshape(E, 3 * C), dst, N).reshape(N, 3, C)
    gate = _sigmoid(agg0)
    out1 = agg1 * gate[:, None, :]
    return torch.concatenate([agg0, out1.reshape(N, 3 * C)], axis=-1)
```

```cpp
#include <cuda_runtime.h>
#include <cuda_bf16.h>
#include <stdint.h>

namespace {

constexpr int NN = 25000;
constexpr int EE = 800000;
constexpr int NBINS = 132;
constexpr int MAXN = 192;
constexpr int CHUNK = 6064;
constexpr int NT = 512;
constexpr int XROWS = 192;
constexpr int GCAP = 1056;
constexpr int LCAP = 6912;
constexpr int BLKCAP = CHUNK + 3 * NBINS + 4;
constexpr int NBUF = 2;
constexpr int PCOMB = 144;
constexpr int PNODE = 11 * PCOMB;
constexpr int PTILE = 16 * PNODE;
constexpr int NST = 2;
constexpr int ROWB = 416;
constexpr int RAWB = 544;
constexpr int STEPB = 8 * ROWB;
constexpr int NGW = 12;
constexpr int MAXT = 12;
constexpr float CSCALE = 7.922816251426434e28f;

__device__ uint4 g_runs[NBINS * BLKCAP * 12 / 16];
__device__ ulonglong4 g_cnt[NBINS * NBINS];
__device__ uint4 g_xc[(NN + 1) * 24];
__device__ ulonglong2 g_flags[NBINS * 4];
__device__ uint4 g_wfrag[20 * 4 * 32];
__device__ ulonglong4 g_bdone[NBINS];
__device__ unsigned int g_epoch;

#define TM(k, i)
#define TMW(k, i)

#define WAIT_FAIL(i) __trap()

__host__ __device__ __forceinline__ int bin_of(int d) { return (d * NBINS) / NN; }
__host__ __device__ __forceinline__ int bin_start(int b) { return (b * NN + NBINS - 1) / NBINS; }

__device__ __forceinline__ uint32_t smem_u32(const void* p) { return (uint32_t)__cvta_generic_to_shared(p); }
__device__ __forceinline__ uint32_t prmt(uint32_t a, uint32_t b, uint32_t s) {
    uint32_t r; asm("prmt.b32 %0, %1, %2, %3;" : "=r"(r) : "r"(a), "r"(b), "r"(s)); return r;
}
__device__ __forceinline__ float bf_lo(uint32_t w) { return __uint_as_float(w << 16); }
__device__ __forceinline__ float bf_hi(uint32_t w) { return __uint_as_float(w & 0xffff0000u); }
__device__ __forceinline__ uint32_t pack_bf(float lo, float hi) {
    uint32_t r; asm("cvt.rn.bf16x2.f32 %0, %1, %2;" : "=r"(r) : "f"(hi), "f"(lo)); return r;
}
__device__ __forceinline__ uint32_t hmul2(uint32_t a, uint32_t b) {
    uint32_t r; asm("mul.rn.bf16x2 %0, %1, %2;" : "=r"(r) : "r"(a), "r"(b)); return r;
}
__device__ __forceinline__ void mma16(float (&d)[4], uint32_t a0, uint32_t a1, uint32_t a2, uint32_t a3, uint32_t b0, uint32_t b1) {
    asm volatile("mma.sync.aligned.m16n8k16.row.col.f32.bf16.bf16.f32 {%0,%1,%2,%3}, {%4,%5,%6,%7}, {%8,%9}, {%0,%1,%2,%3};"
                 : "+f"(d[0]), "+f"(d[1]), "+f"(d[2]), "+f"(d[3]) : "r"(a0), "r"(a1), "r"(a2), "r"(a3), "r"(b0), "r"(b1));
}
__device__ __forceinline__ void mma8(float (&d)[4], uint32_t a0, uint32_t a1, uint32_t b0) {
    asm volatile("mma.sync.aligned.m16n8k8.row.col.f32.bf16.bf16.f32 {%0,%1,%2,%3}, {%4,%5}, {%6}, {%0,%1,%2,%3};"
                 : "+f"(d[0]), "+f"(d[1]), "+f"(d[2]), "+f"(d[3]) : "r"(a0), "r"(a1), "r"(b0));
}
__device__ __forceinline__ uint4 ldg_nc(const void* p) {
    uint4 v; asm volatile("ld.global.nc.v4.u32 {%0,%1,%2,%3}, [%4];" : "=r"(v.x), "=r"(v.y), "=r"(v.z), "=r"(v.w) : "l"(p)); return v;
}
__device__ __forceinline__ void mbar_init(uint32_t bar, uint32_t cnt) { asm volatile("mbarrier.init.shared.b64 [%0], %1;" :: "r"(bar), "r"(cnt) : "memory"); }
__device__ __forceinline__ void mbar_arrive(uint32_t bar) { asm volatile("mbarrier.arrive.shared.b64 _, [%0];" :: "r"(bar) : "memory"); }
__device__ __forceinline__ void mbar_wait(uint32_t bar, uint32_t parity) {
    uint32_t done = 0;
#pragma unroll 1
    for (int it = 0; it < (1 << 28); it++) {
        asm volatile("{.reg .pred p; mbarrier.try_wait.parity.shared.b64 p, [%1], %2; selp.u32 %0, 1, 0, p;}" : "=r"(done) : "r"(bar), "r"(parity) : "memory");
        if (done) return;
    }
    WAIT_FAIL(1);
}

__device__ __forceinline__ void decode4(uint32_t La, uint32_t Lb, uint32_t W, uint32_t (&o)[4], uint32_t k28) {
    const uint32_t Ha = W & 0x87878787u;
    uint32_t lo, hi;
    asm("{ .reg .u64 t; mul.wide.u32 t, %2, %3; mov.b64 {%0, %1}, t; }" : "=r"(lo), "=r"(hi) : "r"(W), "r"(k28));
    const uint32_t Hb = (lo | hi) & 0x87878787u;
    o[0] = prmt(La, Ha, 0x5140); o[1] = prmt(La, Ha, 0x7362);
    o[2] = prmt(Lb, Hb, 0x5140); o[3] = prmt(Lb, Hb, 0x7362);
}
__device__ __forceinline__ uint4 lds128(uint32_t a) {
    uint4 v; asm volatile("ld.shared.v4.u32 {%0,%1,%2,%3}, [%4];" : "=r"(v.x), "=r"(v.y), "=r"(v.z), "=r"(v.w) : "r"(a)); return v;
}
__device__ __forceinline__ uint32_t lds16(uint32_t a) {
    uint32_t v; asm volatile("ld.shared.u16 %0, [%1];" : "=r"(v) : "r"(a)); return v;
}
__device__ __forceinline__ void cp16(uint32_t d, const void* g) {
    asm volatile("cp.async.cg.shared.global [%0], [%1], 16;" :: "r"(d), "l"(g) : "memory");
}
__device__ __forceinline__ void bulk_g2s(uint32_t d, const void* g, uint32_t bytes, uint32_t bar) {
    asm volatile("cp.async.bulk.shared::cluster.global.mbarrier::complete_tx::bytes [%0], [%1], %2, [%3];"
                 :: "r"(d), "l"(g), "r"(bytes), "r"(bar) : "memory");
}
__device__ __forceinline__ void bulk_s2g(void* g, uint32_t sa, uint32_t bytes) {
    asm volatile("cp.async.bulk.global.shared::cta.bulk_group [%0], [%1], %2;" :: "l"(g), "r"(sa), "r"(bytes) : "memory");
}
__device__ __forceinline__ void mbar_expect(uint32_t bar, uint32_t bytes) {
    asm volatile("mbarrier.arrive.expect_tx.shared.b64 _, [%0], %1;" :: "r"(bar), "r"(bytes) : "memory");
}

constexpr int OFF_STG = 0;
constexpr int OFF_P = OFF_STG + NGW * NST * STEPB;
constexpr int OFF_TAB = OFF_P + NBUF * PTILE;
constexpr int TSRC = (GCAP + 1) * 64;
constexpr int TSZ = (GCAP + 1) * 80;
constexpr int OFF_SFL = OFF_TAB + TSZ;
constexpr int OFF_INFO = OFF_SFL + GCAP + 16;
constexpr int OFF_TN = OFF_INFO + 200 * 4;
constexpr int OFF_BAR = OFF_TN + 200 * 2;
constexpr int OFF_MISC = OFF_BAR + 30 * 8;
constexpr int OFF_AUX = OFF_MISC + 64;
constexpr int SMEM_BYTES = OFF_AUX + (132 + 136 + 16 + 8) * 4 + 512;
constexpr int OFF_EDST = 0;
constexpr int OFF_ESRC = OFF_EDST + CHUNK * 4;
constexpr int OFF_EA = OFF_ESRC + CHUNK * 4;
constexpr int OFF_ERH = OFF_EA + CHUNK * 2;
constexpr int OFF_ENT = 0;
constexpr int OFF_LND = 0;
constexpr int OFF_BITS = OFF_LND + LCAP * 12;
constexpr int OFF_H2 = OFF_BITS + 3136;
constexpr int OFF_SEG = OFF_H2 + 2 * MAXN * 4;
constexpr int OFF_RD = OFF_SEG + (LCAP / 4) * 4;
constexpr int OFF_XL = CHUNK * 16;
static_assert(SMEM_BYTES <= 232448, "smem");
static_assert(OFF_ERH + CHUNK * 6 == OFF_XL, "edge inputs");
static_assert(OFF_BAR % 8 == 0 && OFF_P % 16 == 0 && OFF_TAB % 16 == 0 && TSZ % 16 == 0 && TSRC % 16 == 0 && OFF_XL % 128 == 0 && OFF_BITS % 16 == 0 && OFF_AUX % 16 == 0, "align");
static_assert(BLKCAP * 12 <= OFF_BITS && (BLKCAP * 12) % 32 == 0, "entry staging");
static_assert(OFF_RD + 264 * 4 <= OFF_XL, "front tables");
static_assert(OFF_XL + XROWS * 512 <= OFF_INFO && OFF_SFL % 16 == 0, "x landing");
constexpr int BAR_FULL = 0, BAR_FREE = MAXT, BAR_E = 2 * MAXT, BAR_PREP = BAR_E + 2, BAR_BITS = BAR_E + 3, BAR_SCAN = BAR_E + 4;

__device__ __forceinline__ void collect_runs(unsigned char* smem, int b, unsigned int tag, int lane, unsigned long long (&v)[5]) {
    uint32_t* seg = reinterpret_cast<uint32_t*>(smem + OFF_RD);
    int* misc = reinterpret_cast<int*>(smem + OFF_MISC);
    const ulonglong4* cp = g_cnt + (size_t)b * NBINS;
    int c[5];
    for (int it = 0; ; it++) {
        bool ok = true;
#pragma unroll
        for (int i = 0; i < 5; i++) ok = ok && (uint32_t)(v[i] >> 32) == tag;
        if (__all_sync(0xffffffffu, ok)) break;
        if (it > (1 << 24)) WAIT_FAIL(2);
#pragma unroll
        for (int i = 0; i < 5; i++) asm volatile("ld.relaxed.gpu.global.u64 %0, [%1];" : "=l"(v[i]) : "l"(cp + min(lane + 32 * i, NBINS - 1)) : "memory");
    }
    int pre[5], tot = 0;
#pragma unroll
    for (int i = 0; i < 5; i++) {
        c[i] = lane + 32 * i < NBINS ? (int)(v[i] & 0xffff) : 0;
        int incl = c[i];
#pragma unroll
        for (int o = 1; o < 32; o <<= 1) { int w = __shfl_up_sync(0xffffffffu, incl, o); if (lane >= o) incl += w; }
        pre[i] = tot + incl - c[i];
        tot += __shfl_sync(0xffffffffu, incl, 31);
    }
    const bool bad = tot > LCAP;
#pragma unroll
    for (int i = 0; i < 5; i++) {
        const int cc = lane + 32 * i;
        if (cc < NBINS) {
            seg[2 * cc] = bad ? 0u : (uint32_t)(pre[i] >> 2) | ((uint32_t)(c[i] >> 2) << 16);
            seg[2 * cc + 1] = (uint32_t)cc * (BLKCAP * 12) + (uint32_t)((v[i] >> 16) & 0xffff) * 12;
        }
    }
    if (lane == 0) { misc[1] = bad; misc[2] = bad ? 0 : tot; }
}

__global__ void __launch_bounds__(NT, 1)
fused_kernel(const uint4* __restrict__ x, const __nv_bfloat16* __restrict__ rhat, const __nv_bfloat16* __restrict__ ea,
             const int* __restrict__ src, const int* __restrict__ dst,
             const __nv_bfloat16* __restrict__ w_rad, const __nv_bfloat16* __restrict__ w_si0, const __nv_bfloat16* __restrict__ w_si1,
             const __nv_bfloat16* __restrict__ eps, __nv_bfloat16* __restrict__ out) {
    extern __shared__ __align__(128) unsigned char smem[];
    const int tid = threadIdx.x, lane = tid & 31, warp = tid >> 5, b = blockIdx.x;
    const int nstart = bin_start(b);
    const int nn = bin_start(b + 1) - nstart;
    const int ntiles = (nn + 15) >> 4;
    unsigned short* tnode = reinterpret_cast<unsigned short*>(smem + OFF_TN);
    int* misc = reinterpret_cast<int*>(smem + OFF_MISC);
    const uint32_t bar0 = smem_u32(smem + OFF_BAR);
    int kexp;
    const unsigned int epoch = __ldcg(&g_epoch);
    const unsigned int tag = (epoch & 0x7fffu) | 0x8000u;

    TM(0, 0);
    {
        int* hist = reinterpret_cast<int*>(smem + OFF_AUX);
        int* lofs = hist + NBINS;
        uint32_t* smax = reinterpret_cast<uint32_t*>(lofs + 136);
        uint32_t* xfl = smax + 16;
        const int e0 = b * CHUNK;
        const int ne = min(CHUNK, EE - e0);
        const int nq = ne / 4;
        const int xrow0 = b * XROWS;
        const uint32_t bare = bar0 + BAR_E * 8;
        if (tid == 0) {
            for (int t = 0; t < 2; t++) mbar_init(bare + t * 8, 1);
            asm volatile("fence.proxy.async.shared::cta;" ::: "memory");
            const uint32_t s0 = smem_u32(smem);
            mbar_expect(bare, ne * 4);
            bulk_g2s(s0 + OFF_EDST, dst + e0, ne * 4, bare);
            mbar_expect(bare + 8, ne * 12);
            bulk_g2s(s0 + OFF_ESRC, src + e0, ne * 4, bare + 8);
            bulk_g2s(s0 + OFF_EA, ea + e0, ne * 2, bare + 8);
            bulk_g2s(s0 + OFF_ERH, rhat + (size_t)e0 * 3, ne * 6, bare + 8);
        }
        if (tid == 32) {
            for (int t = 0; t < MAXT; t++) {
                mbar_init(bar0 + (BAR_FULL + t) * 8, (uint32_t)max(1, min(16, nn - t * 16)));
                mbar_init(bar0 + (BAR_FREE + t) * 8, 4);
            }
            mbar_init(bar0 + BAR_PREP * 8, 3); mbar_init(bar0 + BAR_BITS * 8, 1); mbar_init(bar0 + BAR_SCAN * 8, 1);
            misc[0] = 0; misc[4] = 0;
        }
        const uint4 samp = __ldg(x + warp * 32 + lane);
        unsigned short wraw[8], wrad[4];
        if (b < 80 && warp == 1) {
            const int ks = b >> 2, w = b & 3, g = lane >> 2, t = lane & 3;
#pragma unroll
            for (int hu = 0; hu < 4; hu++) {
                const int kk = ks * 16 + (hu >> 1) * 8 + 2 * t + (hu & 1);
                wrad[hu] = __bfloat16_as_ushort(w_rad[kk]);
#pragma unroll
                for (int j = 0; j < 2; j++) {
                    const int col = 16 * w + 4 * (g >> 1) + 2 * j + (g & 1);
                    wraw[j * 4 + hu] = __bfloat16_as_ushort(kk < 128 ? w_si0[kk * 64 + col] : w_si1[(kk - 128) * 64 + col]);
                }
            }
        }
        if (tid < NBINS) hist[tid] = 0;
        if (tid < 8) xfl[tid] = 0;
        {
            uint32_t m = 0;
            const uint32_t w[4] = {samp.x, samp.y, samp.z, samp.w};
#pragma unroll
            for (int i = 0; i < 4; i++) { m = max(m, w[i] & 0x7fffu); m = max(m, (w[i] >> 16) & 0x7fffu); }
            m = __reduce_max_sync(0xffffffffu, m);
            if (lane == 0) smax[warp] = m;
        }
        __syncthreads();
        mbar_wait(bare, 0);
        int4 d4[3]; int rank[12];
#pragma unroll
        for (int i = 0; i < 3; i++) {
            if (tid + i * NT < nq) {
                d4[i] = reinterpret_cast<const int4*>(smem + OFF_EDST)[tid + i * NT];
                const int dd[4] = {d4[i].x, d4[i].y, d4[i].z, d4[i].w};
#pragma unroll
                for (int u = 0; u < 4; u++) {
                    const int bb = bin_of(dd[u]);
                    rank[4 * i + u] = atomicAdd(&hist[bb], 1) | (bb << 16);
                }
            }
        }
        __syncthreads();
        TM(0, 1);
        if (warp == 0) {
            int c[5], sum = 0;
#pragma unroll
            for (int i = 0; i < 5; i++) { const int bb = lane * 5 + i; c[i] = bb < NBINS ? (hist[bb] + 3) & ~3 : 0; sum += c[i]; }
            int incl = sum;
#pragma unroll
            for (int o = 1; o < 32; o <<= 1) { int v = __shfl_up_sync(0xffffffffu, incl, o); if (lane >= o) incl += v; }
            int run = incl - sum;
#pragma unroll
            for (int i = 0; i < 5; i++) { const int bb = lane * 5 + i; if (bb <= NBINS) lofs[bb] = run; run += c[i]; }
            __syncwarp();
            if (lane == 0) mbar_arrive(bar0 + BAR_SCAN * 8);
#pragma unroll
            for (int i = 0; i < 9; i++) {
                const int r = (lane >> 1) + 16 * i;
                if (r < NBINS) {
                    const unsigned long long v = ((unsigned long long)tag << 32) | ((unsigned long long)lofs[r] << 16) | (unsigned int)((hist[r] + 3) & ~3);
                    asm volatile("st.relaxed.gpu.global.v2.u64 [%0], {%1, %1};" :: "l"(reinterpret_cast<ulonglong2*>(&g_cnt[(size_t)r * NBINS + b]) + (lane & 1)), "l"(v) : "memory");
                }
            }
        }
        uint32_t mx = 0;
#pragma unroll
        for (int i = 0; i < 16; i++) mx = max(mx, smax[i]);
        {
            const float f = __uint_as_float(mx << 16) * 1.25f;
            const int e = (__float_as_uint(f) >> 23) & 0xff;
            kexp = 15 - max(60, min(141, e));
        }
        if (b < 80 && warp == 1) {
            const float sc = __uint_as_float((uint32_t)(31 - kexp) << 23);
            uint32_t o[4];
#pragma unroll
            for (int j = 0; j < 2; j++)
#pragma unroll
                for (int h = 0; h < 2; h++)
                    o[j * 2 + h] = pack_bf(__uint_as_float((uint32_t)wraw[j * 4 + h * 2] << 16) * __uint_as_float((uint32_t)wrad[h * 2] << 16) * sc,
                                           __uint_as_float((uint32_t)wraw[j * 4 + h * 2 + 1] << 16) * __uint_as_float((uint32_t)wrad[h * 2 + 1] << 16) * sc);
            uint4* wst = reinterpret_cast<uint4*>(xfl + 8);
            wst[lane] = make_uint4(o[0], o[1], o[2], o[3]);
            asm volatile("fence.proxy.async.shared::cta;" ::: "memory");
            __syncwarp();
            if (lane == 0) {
                bulk_s2g(g_wfrag + b * 32, smem_u32(wst), 512);
                asm volatile("cp.async.bulk.commit_group;" ::: "memory");
            }
        }
        mbar_wait(bare + 8, 0);
        if (warp < 12) {
#pragma unroll
            for (int j = 0; j < 16; j++) {
                const int row = xrow0 + warp * 16 + j;
                if (row < NN) cp16(smem_u32(smem + OFF_XL) + (warp * 16 + j) * 512 + lane * 16, x + (size_t)row * 32 + lane);
                if ((j & 7) == 7) asm volatile("cp.async.commit_group;" ::: "memory");
            }
        }
        mbar_wait(bar0 + BAR_SCAN * 8, 0);
        uint32_t ek[12], ec0[12], ec1[12];
        bool nonfinite = false;
#pragma unroll
        for (int i = 0; i < 3; i++) {
            const int q = tid + i * NT;
            if (q < nq) {
                const int4 s4 = reinterpret_cast<const int4*>(smem + OFF_ESRC)[q];
                const uint2 a2 = reinterpret_cast<const uint2*>(smem + OFF_EA)[q];
                const uint2* rp = reinterpret_cast<const uint2*>(smem + OFF_ERH) + 3 * q;
                const uint2 r0 = rp[0], r1 = rp[1], r2 = rp[2];
                const int dd[4] = {d4[i].x, d4[i].y, d4[i].z, d4[i].w};
                const int ss[4] = {s4.x, s4.y, s4.z, s4.w};
                const uint32_t aw[2] = {a2.x, a2.y};
                const uint32_t rw[6] = {r0.x, r0.y, r1.x, r1.y, r2.x, r2.y};
#pragma unroll
                for (int u = 0; u < 4; u++) {
                    const float a = ((u & 1) ? bf_hi(aw[u >> 1]) : bf_lo(aw[u >> 1])) * CSCALE;
                    float y[3];
#pragma unroll
                    for (int j = 0; j < 3; j++) { const int h = 3 * u + j; y[j] = (h & 1) ? bf_hi(rw[h >> 1]) : bf_lo(rw[h >> 1]); }
                    ek[4 * i + u] = (uint32_t)ss[u] | ((uint32_t)dd[u] << 16);
                    const uint32_t c0 = pack_bf(a, a * y[0]), c1 = pack_bf(a * y[1], a * y[2]);
                    ec0[4 * i + u] = c0; ec1[4 * i + u] = c1;
                    nonfinite |= ((c0 & 0x7f80u) == 0x7f80u) | ((c0 & 0x7f800000u) == 0x7f800000u) | ((c1 & 0x7f80u) == 0x7f80u) | ((c1 & 0x7f800000u) == 0x7f800000u);
                    rank[4 * i + u] = (lofs[rank[4 * i + u] >> 16] + (rank[4 * i + u] & 0xffff)) * 12;
                }
            }
        }
        __syncthreads();
        TM(0, 6);
        unsigned long long rdesc[5];
        if (warp == 14) {
#pragma unroll
            for (int i = 0; i < 5; i++) asm volatile("ld.relaxed.gpu.global.u64 %0, [%1];" : "=l"(rdesc[i]) : "l"(g_cnt + (size_t)b * NBINS + min(lane + 32 * i, NBINS - 1)) : "memory");
        }
        uint32_t* ent = reinterpret_cast<uint32_t*>(smem + OFF_ENT);
#pragma unroll
        for (int i = 0; i < 12; i++) {
            if (tid + (i >> 2) * NT < nq) {
                uint32_t* ep = reinterpret_cast<uint32_t*>(smem + OFF_ENT + rank[i]);
                ep[0] = ek[i]; ep[1] = ec0[i]; ep[2] = ec1[i];
            }
        }
        if (nonfinite) misc[4] = 1;
        if (tid < NBINS) {
            const int c = hist[tid], o = lofs[tid];
            for (int i = c; i < ((c + 3) & ~3); i++) ent[(o + i) * 3] = 0xffffffffu;
        }
        asm volatile("fence.proxy.async.shared::cta;" ::: "memory");
        __syncthreads();
        TM(0, 2);
        if (warp >= 12) {
            if (warp == 15) {
                if (lane == 0) {
                    bulk_s2g(reinterpret_cast<unsigned char*>(g_runs) + (size_t)b * (BLKCAP * 12), smem_u32(smem + OFF_ENT), (lofs[NBINS] * 12 + 31) & ~31);
                    asm volatile("cp.async.bulk.commit_group;" ::: "memory");
                    asm volatile("cp.async.bulk.wait_group 0;" ::: "memory");
                    asm volatile("fence.proxy.async.global;" ::: "memory");
                }
                asm volatile("bar.sync 5, 416;" ::: "memory");
                if (lane == 0) asm volatile("st.release.gpu.global.u64 [%0], %1;" :: "l"(&g_bdone[b]), "l"(((unsigned long long)tag << 32) | (unsigned int)misc[4]) : "memory");
                __syncwarp();
                TMW(0, 5);
            } else if (warp == 12) {
                for (int i = lane; i < 2 * MAXN; i += 32) reinterpret_cast<int*>(smem + OFF_H2)[i] = 0;
            }
            if (warp == 12 || warp == 14) {
                if (warp == 14) { collect_runs(smem, b, tag, lane, rdesc); TMW(1, 0); }
                asm volatile("bar.sync 2, 64;" ::: "memory");
                uint32_t* blk = reinterpret_cast<uint32_t*>(smem + OFF_SEG);
                for (int cc = (warp == 14 ? 32 : 0) + lane; cc < NBINS; cc += 64) {
                    const uint2 d = reinterpret_cast<const uint2*>(smem + OFF_RD)[cc];
                    uint32_t* bp = blk + (d.x & 0xffff);
                    const int nb = d.x >> 16;
#pragma unroll 4
                    for (int j = 0; j < nb; j++) bp[j] = d.y + j * 48;
                }
                __syncwarp();
                if (lane == 0) mbar_arrive(bar0 + BAR_PREP * 8);
            } else if (warp == 15) {
                if (lane == 0) mbar_arrive(bar0 + BAR_PREP * 8);
            }
            if (warp == 13) {
                unsigned long long bw[25];
                for (int it = 0; ; it++) {
                    bool ok = true;
#pragma unroll
                    for (int i = 0; i < 25; i++) {
                        const int wd = min(lane + 32 * i, NBINS * 6 - 1);
                        asm volatile("ld.relaxed.gpu.global.u64 %0, [%1];" : "=l"(bw[i]) : "l"(reinterpret_cast<const unsigned long long*>(g_flags) + (wd / 6) * 8 + wd % 6) : "memory");
                    }
#pragma unroll
                    for (int i = 0; i < 25; i++) ok = ok && (uint32_t)(bw[i] >> 32) == tag;
                    if (__all_sync(0xffffffffu, ok)) break;
                    if (it > (1 << 24)) WAIT_FAIL(3);
                }
#pragma unroll
                for (int i = 0; i < 25; i++) if (lane + 32 * i < 782) reinterpret_cast<uint32_t*>(smem + OFF_BITS)[lane + 32 * i] = (uint32_t)bw[i];
                __syncwarp();
                if (lane == 0) mbar_arrive(bar0 + BAR_BITS * 8);
                TMW(0, 12);
            }
        } else {
            const uint32_t sdn = ((uint32_t)(127 + kexp) << 7) * 0x10001u, sup = ((uint32_t)(127 - kexp) << 7) * 0x10001u;
            const int r = lane >> 3, g = lane & 7;
            unsigned char* slot = smem + OFF_XL + warp * 16 * 512;
            uint32_t fl = 0;
#pragma unroll
            for (int c = 0; c < 4; c++) {
                if (c == 0) asm volatile("cp.async.wait_group 1;" ::: "memory");
                if (c == 2) asm volatile("cp.async.wait_group 0;" ::: "memory");
                __syncwarp();
                if (warp == 0) TMW(1, 20 + c);
                uint4 xv[4];
#pragma unroll
                for (int j = 0; j < 4; j++) xv[j] = *reinterpret_cast<const uint4*>(slot + (c * 4 + j) * 512 + lane * 16);
                __syncwarp();
#pragma unroll
                for (int j = 0; j < 4; j++) {
                    const int row = xrow0 + warp * 16 + c * 4 + j;
                    const uint32_t y0 = hmul2(xv[j].x, sdn), y1 = hmul2(xv[j].y, sdn), y2 = hmul2(xv[j].z, sdn), y3 = hmul2(xv[j].w, sdn);
                    const uint32_t bad = ((y0 | y1 | y2 | y3) & 0x78007800u) | (hmul2(y0, sup) ^ xv[j].x) | (hmul2(y1, sup) ^ xv[j].y) |
                                         (hmul2(y2, sup) ^ xv[j].z) | (hmul2(y3, sup) ^ xv[j].w);
                    const uint32_t La = prmt(y0, y1, 0x6420), Lb = prmt(y2, y3, 0x6420);
                    const uint32_t Ha = prmt(y0, y1, 0x7531) & 0x87878787u, Hb = prmt(y2, y3, 0x7531) & 0x87878787u;
                    const uint32_t W = Ha | __funnelshift_l(Hb, Hb, 4);
                    unsigned char* rp = slot + (c * 4 + j) * 384;
                    *reinterpret_cast<uint2*>(rp + (r >> 1) * 128 + g * 16 + (r & 1) * 8) = make_uint2(La, Lb);
                    *reinterpret_cast<uint32_t*>(rp + 256 + g * 16 + r * 4) = W;
                    if (__any_sync(0xffffffffu, bad != 0) && row < NN) fl |= 1u << (c * 4 + j);
                }
            }
            if (lane == 0 && fl) atomicOr(&xfl[warp >> 1], fl << ((warp & 1) * 16));
            if (warp == 0) TMW(0, 20);
            asm volatile("bar.sync 1, 384;" ::: "memory");
            if (warp == 0) {
                if (lane < 4) {
                    const unsigned long long v0 = ((unsigned long long)tag << 32) | xfl[2 * lane], v1 = ((unsigned long long)tag << 32) | xfl[2 * lane + 1];
                    asm volatile("st.relaxed.gpu.global.v2.u64 [%0], {%1, %2};" :: "l"(&g_flags[b * 4 + lane]), "l"(v0), "l"(v1) : "memory");
                }
                TMW(0, 3);
            }
            asm volatile("fence.proxy.async.shared::cta;" ::: "memory");
            __syncwarp();
            if (lane == 0) {
                const int row = xrow0 + warp * 16;
                const int nr = min(16, NN - row);
                if (nr > 0) bulk_s2g(reinterpret_cast<unsigned char*>(g_xc) + (size_t)row * 384, smem_u32(slot), nr * 384);
                asm volatile("cp.async.bulk.commit_group;" ::: "memory");
                asm volatile("cp.async.bulk.wait_group 0;" ::: "memory");
                asm volatile("fence.proxy.async.global;" ::: "memory");
            }
            asm volatile("bar.sync 5, 416;" ::: "memory");
            for (int i = tid; i < TSRC / 16; i += 384) reinterpret_cast<uint4*>(smem + OFF_TAB)[i] = make_uint4(0, 0, 0, 0);
            const uint32_t dm = (uint32_t)NN | ((uint32_t)NN << 16);
            for (int i = tid; i < GCAP + 1; i += 384) reinterpret_cast<uint4*>(smem + OFF_TAB + TSRC)[i] = make_uint4(dm, dm, dm, dm);
            for (int i = tid; i < GCAP / 16 + 1; i += 384) reinterpret_cast<uint4*>(smem + OFF_SFL)[i] = make_uint4(0, 0, 0, 0);
        }
    }
    TM(1, 1);
    {
        int* hist2 = reinterpret_cast<int*>(smem + OFF_H2);
        const uint32_t* bits = reinterpret_cast<const uint32_t*>(smem + OFF_BITS);
        uint32_t* info = reinterpret_cast<uint32_t*>(smem + OFF_INFO);
        unsigned char* tab = smem + OFF_TAB;
        mbar_wait(bar0 + BAR_PREP * 8, 0);
        TM(0, 13);
        const int nblk = misc[2] >> 2;
        const int per = (nblk + 15) >> 4;
        const int q0 = warp * per, q1 = min(nblk, q0 + per);
        if (q0 < q1) {
            const uint32_t* blk = reinterpret_cast<const uint32_t*>(smem + OFF_SEG);
            const int c0 = blk[q0] / (BLKCAP * 12), c1 = blk[q1 - 1] / (BLKCAP * 12);
            for (int cb = c0; cb <= c1; cb += 32) {
                unsigned long long v;
                for (int it = 0; ; it++) {
                    asm volatile("ld.acquire.gpu.global.u64 %0, [%1];" : "=l"(v) : "l"(&g_bdone[min(cb + lane, c1)]) : "memory");
                    if (__all_sync(0xffffffffu, (uint32_t)(v >> 32) == tag)) break;
                    if (it > (1 << 24)) WAIT_FAIL(4);
                }
                if ((uint32_t)v) misc[1] = 1;
            }
            TM(0, 14);
            const unsigned char* gb = reinterpret_cast<const unsigned char*>(g_runs);
            const uint32_t lnd = smem_u32(smem + OFF_LND);
#pragma unroll
            for (int i = 0; i < 11; i++) {
                const int c = q0 * 3 + lane + 32 * i;
                if (c < q1 * 3) { const int bk = c / 3; cp16(lnd + c * 16, gb + blk[bk] + (c - 3 * bk) * 16); }
            }
        }
        TM(0, 15);
        asm volatile("cp.async.wait_all;" ::: "memory");
        __syncwarp();
        TM(0, 7);
        mbar_wait(bar0 + BAR_BITS * 8, 0);
        int rank[16]; uint32_t esrc[16]; uint2 ecf[16];
#pragma unroll
        for (int i = 0; i < 4; i++) {
            const int qd = q0 + lane + 32 * i;
#pragma unroll
            for (int u = 0; u < 4; u++) rank[4 * i + u] = -1;
            if (qd < q1) {
                const uint4* ep = reinterpret_cast<const uint4*>(smem + OFF_LND + qd * 48);
                const uint4 a = ep[0], bq = ep[1], c = ep[2];
                const uint32_t key[4] = {a.x, a.w, bq.z, c.y};
                ecf[4 * i] = make_uint2(a.y, a.z); ecf[4 * i + 1] = make_uint2(bq.x, bq.y);
                ecf[4 * i + 2] = make_uint2(bq.w, c.x); ecf[4 * i + 3] = make_uint2(c.z, c.w);
#pragma unroll
                for (int u = 0; u < 4; u++) {
                    esrc[4 * i + u] = key[u] & 0xffff;
                    if (key[u] != 0xffffffffu) {
                        const int sr = key[u] & 0xffff;
                        const int fl = (bits[sr >> 5] >> (sr & 31)) & 1;
                        const int cls = ((int)(key[u] >> 16) - nstart) * 2 + fl;
                        rank[4 * i + u] = atomicAdd(&hist2[cls], 1) | (cls << 16);
                    }
                }
            }
        }
        __syncthreads();
        if (b == 0 && tid == 0) g_epoch = epoch + 1;
        TM(0, 8);
        if (warp == 0) {
            int gc[6], gr[6], sum = 0;
#pragma unroll
            for (int i = 0; i < 6; i++) {
                const int n = lane * 6 + i;
                gc[i] = (hist2[2 * n] + 7) >> 3; gr[i] = (hist2[2 * n + 1] + 3) >> 2;
                if (gc[i] + gr[i] == 0 && n < nn) gc[i] = 1;
                sum += gc[i] + gr[i];
            }
            int incl = sum;
#pragma unroll
            for (int o = 1; o < 32; o <<= 1) { int v = __shfl_up_sync(0xffffffffu, incl, o); if (lane >= o) incl += v; }
            const int tot = __shfl_sync(0xffffffffu, incl, 31);
            const bool fb = misc[1] || tot > GCAP;
            int run = incl - sum;
#pragma unroll
            for (int i = 0; i < 6; i++) {
                info[lane * 6 + i] = (uint32_t)run | ((uint32_t)(run + gc[i]) << 16);
                run += gc[i] + gr[i];
            }
            __syncwarp();
            if (lane == 31) { info[MAXN] = (uint32_t)run; misc[1] = fb; }
        }
        __syncthreads();
        TM(0, 10);
        unsigned long long xd[5];
        if (warp == 13) {
#pragma unroll
            for (int i = 0; i < 5; i++) asm volatile("ld.acquire.gpu.global.u64 %0, [%1];" : "=l"(xd[i]) : "l"(&g_bdone[min(lane + 32 * i, NBINS - 1)]) : "memory");
        }
        if (!misc[1]) {
            if (tid < nn) {
                const uint32_t inf = info[tid];
                const int r0 = inf >> 16, e = info[tid + 1] & 0xffff;
                unsigned short* sp = reinterpret_cast<unsigned short*>(tab + TSRC);
                int left = hist2[2 * tid + 1];
                for (int p = r0; p < e; p++, left -= 4) {
                    for (int k = max(0, min(4, left)); k < 8; k++) sp[p * 8 + k] = (unsigned short)(NN | 0x8000);
                    smem[OFF_SFL + p] = (p == e - 1) ? 3 : 1;
                }
                if (r0 == e) smem[OFF_SFL + e - 1] = 2;
            }
            const uint32_t sc2 = ((uint32_t)(127 + kexp) << 7) * 0x10001u;
#pragma unroll
            for (int i = 0; i < 16; i++) {
                if (rank[i] >= 0) {
                    const int cls = rank[i] >> 16, rk = rank[i] & 0xffff;
                    const uint32_t inf = info[cls >> 1];
                    int pos; uint2 c = ecf[i]; uint32_t sv = esrc[i];
                    if (cls & 1) {
                        pos = ((inf >> 16) + (rk >> 2)) * 8 + (rk & 3);
                        c.x = hmul2(c.x, sc2); c.y = hmul2(c.y, sc2); sv |= 0x8000u;
                    } else pos = (inf & 0xffff) * 8 + rk;
                    reinterpret_cast<unsigned short*>(tab + TSRC)[pos] = (unsigned short)sv;
                    reinterpret_cast<uint2*>(tab)[pos] = c;
                }
            }
        }
        if (warp == 13) {
            for (int it = 0; ; it++) {
                bool ok = true;
#pragma unroll
                for (int i = 0; i < 5; i++) ok = ok && (uint32_t)(xd[i] >> 32) == tag;
                if (__all_sync(0xffffffffu, ok)) break;
                if (it > (1 << 24)) WAIT_FAIL(5);
#pragma unroll
                for (int i = 0; i < 5; i++) asm volatile("ld.acquire.gpu.global.u64 %0, [%1];" : "=l"(xd[i]) : "l"(&g_bdone[min(lane + 32 * i, NBINS - 1)]) : "memory");
            }
        }
        __syncthreads();
    }
    TM(1, 2);

    if (warp < NGW) {
        const int g = lane >> 2, t = lane & 3;
        uint32_t ca[4];
        {
            float v[2][4];
#pragma unroll
            for (int hh = 0; hh < 2; hh++) {
                const int m = g + 8 * hh;
#pragma unroll
                for (int r = 0; r < 4; r++) {
                    float c = 0.f;
                    if (m == 0) c = (t == 0 && r == 0) ? 1.f : 0.f;
                    else if (m == 1) c = (t >= 1 && r == t) ? 1.f : 0.f;
                    else if (m < 5) c = (t == m - 1 && r == 0) ? 1.f : 0.f;
                    else if (m < 8) c = (t == 0 && r == m - 4) ? 1.f : 0.f;
                    else if (m < 11) c = (t >= 1 && r >= 1) ? __bfloat162float(eps[(m - 8) * 9 + (t - 1) * 3 + (r - 1)]) : 0.f;
                    v[hh][r] = c;
                }
            }
            ca[0] = pack_bf(v[0][0], v[0][1]); ca[1] = pack_bf(v[1][0], v[1][1]);
            ca[2] = pack_bf(v[0][2], v[0][3]); ca[3] = pack_bf(v[1][2], v[1][3]);
        }
        float acc[4][2][4];
#pragma unroll
        for (int r = 0; r < 4; r++)
#pragma unroll
            for (int h = 0; h < 2; h++)
#pragma unroll
                for (int i = 0; i < 4; i++) acc[r][h][i] = 0.f;
        const int psh = (g & 1) * 16;

        auto generic_node = [&](int node) {
            const unsigned char* xr = reinterpret_cast<const unsigned char*>(x) + g * 16;
            const float sc = __uint_as_float((uint32_t)(127 + 96 + kexp) << 23);
            const int gn = nstart + node;
            for (int e0 = 0; e0 < EE; e0 += 32) {
                unsigned m = __ballot_sync(0xffffffffu, dst[e0 + lane] == gn);
                while (m) {
                    const int e = e0 + __ffs(m) - 1; m &= m - 1;
                    uint32_t bq = 0; uint4 v[4];
#pragma unroll
                    for (int r = 0; r < 4; r++) v[r] = make_uint4(0, 0, 0, 0);
                    if (t == 0) {
                        const float a = __bfloat162float(ea[e]);
                        const int q = g >> 1;
                        const float cf = __bfloat162float(__float2bfloat16_rn(q == 0 ? a : a * __bfloat162float(rhat[3 * e + q - 1])));
                        bq = (pack_bf(cf * sc, 0.f) & 0xffffu) << psh;
                        const unsigned char* r0 = xr + (size_t)src[e] * 512;
#pragma unroll
                        for (int r = 0; r < 4; r++) v[r] = ldg_nc(r0 + r * 128);
                    }
#pragma unroll
                    for (int r = 0; r < 4; r++) { mma8(acc[r][0], v[r].x, v[r].y, bq); mma8(acc[r][1], v[r].z, v[r].w, bq); }
                }
            }
        };
        int nslot = 0;
        const uint32_t slot_ctr = smem_u32(&misc[0]);
        auto take_slot = [&]() { if (lane == 0) asm volatile("atom.shared.add.u32 %0, [%1], 1;" : "=r"(nslot) : "r"(slot_ctr) : "memory"); };
        auto finalize = [&](int node, bool more) {
            const int slot = __shfl_sync(0xffffffffu, nslot, 0);
            if (more) take_slot();
            float p0[8][4];
#pragma unroll
            for (int c = 0; c < 8; c++) {
                const uint32_t b0 = pack_bf(acc[0][c >> 2][c & 3], acc[1][c >> 2][c & 3]);
                const uint32_t b1 = pack_bf(acc[2][c >> 2][c & 3], acc[3][c >> 2][c & 3]);
                p0[c][0] = p0[c][1] = p0[c][2] = p0[c][3] = 0.f;
                mma16(p0[c], ca[0], ca[1], ca[2], ca[3], b0, b1);
            }
            const int tile = slot >> 4;
            if (tile >= NBUF) mbar_wait(bar0 + (BAR_FREE + tile - NBUF) * 8, 0);
            unsigned char* pb = smem + OFF_P + (tile % NBUF) * PTILE + (slot & 15) * PNODE + g * PCOMB + t * 32;
            *reinterpret_cast<uint4*>(pb) = make_uint4(pack_bf(p0[0][0], p0[1][0]), pack_bf(p0[2][0], p0[3][0]), pack_bf(p0[4][0], p0[5][0]), pack_bf(p0[6][0], p0[7][0]));
            *reinterpret_cast<uint4*>(pb + 16) = make_uint4(pack_bf(p0[0][1], p0[1][1]), pack_bf(p0[2][1], p0[3][1]), pack_bf(p0[4][1], p0[5][1]), pack_bf(p0[6][1], p0[7][1]));
            if (g < 3) {
                *reinterpret_cast<uint4*>(pb + 8 * PCOMB) = make_uint4(pack_bf(p0[0][2], p0[1][2]), pack_bf(p0[2][2], p0[3][2]), pack_bf(p0[4][2], p0[5][2]), pack_bf(p0[6][2], p0[7][2]));
                *reinterpret_cast<uint4*>(pb + 8 * PCOMB + 16) = make_uint4(pack_bf(p0[0][3], p0[1][3]), pack_bf(p0[2][3], p0[3][3]), pack_bf(p0[4][3], p0[5][3]), pack_bf(p0[6][3], p0[7][3]));
            }
            if (lane == 0) tnode[slot] = (unsigned short)node;
            __syncwarp();
            if (lane == 0) mbar_arrive(bar0 + (BAR_FULL + tile) * 8);
#pragma unroll
            for (int r = 0; r < 4; r++)
#pragma unroll
                for (int h = 0; h < 2; h++)
#pragma unroll
                    for (int i = 0; i < 4; i++) acc[r][h][i] = 0.f;
        };

        if (!misc[1]) {
            const uint32_t* info = reinterpret_cast<const uint32_t*>(smem + OFF_INFO);
            const int stot = info[MAXN] & 0xffff;
            int nlo = 0, nhi = 0;
            for (int n0 = 0; n0 < MAXN; n0 += 32) {
                const int n = n0 + lane;
                const int own = n < nn ? (((int)(info[n] & 0xffff) + (int)(info[n + 1] & 0xffff) + 2 * n + 1) * NGW) / (2 * stot + 2 * nn) : NGW;
                nlo += __popc(__ballot_sync(0xffffffffu, own < warp));
                nhi += __popc(__ballot_sync(0xffffffffu, own <= warp));
            }
            const int p0 = info[nlo] & 0xffff, pend = info[nhi] & 0xffff;
            const uint32_t stg0 = smem_u32(smem + OFF_STG) + warp * (NST * STEPB);
            const unsigned char* gsrc[3]; uint32_t sdst[3], ssel[3];
#pragma unroll
            for (int i = 0; i < 3; i++) {
                const int c = 32 * i + lane, row = c / 24, off = (c - 24 * row) * 16;
                const unsigned char* gp = reinterpret_cast<const unsigned char*>(g_xc) + off;
                asm volatile("mov.b64 %0, %1;" : "=l"(gsrc[i]) : "l"(gp));
                sdst[i] = stg0 + row * ROWB + off;
                ssel[i] = (2 * row) | ((2 * row + 1) << 4) | ((8 | (2 * row + 1)) << 8) | ((8 | (2 * row + 1)) << 12);
            }
            const unsigned char* xr16;
            asm volatile("mov.b64 %0, %1;" : "=l"(xr16) : "l"(reinterpret_cast<const unsigned char*>(x) + lane * 16));
            const uint32_t rdst = stg0 + lane * 16;
            const uint32_t lda = stg0 + t * ROWB + g * 16, ldr = stg0 + t * RAWB + g * 16;
            uint32_t psrc = smem_u32(smem + OFF_TAB + TSRC) + p0 * 16;
            uint32_t ccf = smem_u32(smem + OFF_TAB) + p0 * 64 + t * 8 + (g >> 1) * 2;
            uint32_t cfl = smem_u32(smem + OFF_SFL) + p0;
            int left = pend - p0;
            const uint32_t dsrc = smem_u32(smem + OFF_TAB + TSRC) + GCAP * 16;
            uint4 sw;
            auto meta = [&](const int k) {
                const uint32_t a = left > k ? psrc + k * 16 : dsrc;
                sw = lds128(a);
            };
            auto cp16z = [&](uint32_t d, const unsigned char* gp, uint32_t sv, uint32_t dummy) {
                asm volatile("{ .reg .pred p; setp.eq.u32 p, %2, %3; cp.async.cg.shared.global [%0], [%1], 16, p; }"
                             :: "r"(d), "l"(gp), "r"(sv), "r"(dummy) : "memory");
            };
            auto issue_packed = [&](const int stage) {
                const uint32_t s0 = prmt(sw.x, sw.y, ssel[0]), s1 = prmt(sw.x, sw.y, ssel[1]), s2 = prmt(sw.x, sw.y, ssel[2]);
                const uint32_t s3 = prmt(sw.z, sw.w, ssel[0]), s4 = prmt(sw.z, sw.w, ssel[1]), s5 = prmt(sw.z, sw.w, ssel[2]);
                cp16z(sdst[0] + stage * STEPB, gsrc[0] + (size_t)s0 * 384, s0, NN);
                cp16z(sdst[1] + stage * STEPB, gsrc[1] + (size_t)s1 * 384, s1, NN);
                cp16z(sdst[2] + stage * STEPB, gsrc[2] + (size_t)s2 * 384, s2, NN);
                cp16z(sdst[0] + stage * STEPB + 4 * ROWB, gsrc[0] + (size_t)s3 * 384, s3, NN);
                cp16z(sdst[1] + stage * STEPB + 4 * ROWB, gsrc[1] + (size_t)s4 * 384, s4, NN);
                cp16z(sdst[2] + stage * STEPB + 4 * ROWB, gsrc[2] + (size_t)s5 * 384, s5, NN);
            };
            auto issue = [&](const int stage) {
                if (!(sw.x & 0x8000u)) issue_packed(stage);
                else {
                    const uint32_t s0 = sw.x & 0x7fffu, s1 = (sw.x >> 16) & 0x7fffu, s2 = sw.y & 0x7fffu, s3 = (sw.y >> 16) & 0x7fffu;
                    cp16z(rdst + stage * STEPB, xr16 + (size_t)s0 * 512, s0, NN);
                    cp16z(rdst + stage * STEPB + RAWB, xr16 + (size_t)s1 * 512, s1, NN);
                    cp16z(rdst + stage * STEPB + 2 * RAWB, xr16 + (size_t)s2 * 512, s2, NN);
                    cp16z(rdst + stage * STEPB + 3 * RAWB, xr16 + (size_t)s3 * 512, s3, NN);
                }
                asm volatile("cp.async.commit_group;" ::: "memory");
            };
            uint32_t k28;
            asm volatile("mov.u32 %0, 0x10000000;" : "=r"(k28));
            meta(0); issue(0); meta(1); issue(1); meta(2);
            psrc += 3 * 16; left -= 3;
            int node = nlo;
            uint32_t b0 = lds16(ccf) << psh, b1 = lds16(ccf + 32) << psh, fc;
            asm volatile("ld.shared.u8 %0, [%1];" : "=r"(fc) : "r"(cfl));
#define NEXT_MODE() ((fc & 3) | ((sw.x >> 15) & 1))
            uint32_t mode = NEXT_MODE();
            auto packed_mma = [&](const uint4& l0, const uint4& l1, const uint4& w, const uint4& m0, const uint4& m1, const uint4& v,
                                  uint32_t (&u)[4], uint32_t (&z)[4], uint32_t c0, uint32_t c1) {
                mma16(acc[0][0], u[0], u[1], z[0], z[1], c0, c1); mma16(acc[0][1], u[2], u[3], z[2], z[3], c0, c1);
                decode4(l0.z, l0.w, w.y, u, k28); decode4(m0.z, m0.w, v.y, z, k28);
                mma16(acc[1][0], u[0], u[1], z[0], z[1], c0, c1); mma16(acc[1][1], u[2], u[3], z[2], z[3], c0, c1);
                decode4(l1.x, l1.y, w.z, u, k28); decode4(m1.x, m1.y, v.z, z, k28);
                mma16(acc[2][0], u[0], u[1], z[0], z[1], c0, c1); mma16(acc[2][1], u[2], u[3], z[2], z[3], c0, c1);
                decode4(l1.z, l1.w, w.w, u, k28); decode4(m1.z, m1.w, v.w, z, k28);
                mma16(acc[3][0], u[0], u[1], z[0], z[1], c0, c1); mma16(acc[3][1], u[2], u[3], z[2], z[3], c0, c1);
            };
            uint32_t mcur;
            auto fast_body = [&](const int stage) {
                const uint32_t c0 = b0, c1 = b1;
                const uint32_t a = lda + stage * STEPB;
                const uint4 l0 = lds128(a), l1 = lds128(a + 128), w = lds128(a + 256);
                const uint4 m0 = lds128(a + 4 * ROWB), m1 = lds128(a + 4 * ROWB + 128), v = lds128(a + 4 * ROWB + 256);
                b0 = lds16(ccf + (stage + 1) * 64) << psh; b1 = lds16(ccf + (stage + 1) * 64 + 32) << psh;
                asm volatile("ld.shared.u8 %0, [%1];" : "=r"(fc) : "r"(cfl + stage + 1));
                uint32_t u[4], z[4];
                decode4(l0.x, l0.y, w.x, u, k28); decode4(m0.x, m0.y, v.x, z, k28);
                issue_packed(stage);
                asm volatile("cp.async.commit_group;" ::: "memory");
                meta(stage);
                packed_mma(l0, l1, w, m0, m1, v, u, z, c0, c1);
            };
            auto slow_body = [&](const int stage) {
                const uint32_t fcur = fc, c0 = b0, c1 = b1;
                if (!(fcur & 1)) {
                    const uint32_t a = lda + stage * STEPB;
                    const uint4 l0 = lds128(a), l1 = lds128(a + 128), w = lds128(a + 256);
                    const uint4 m0 = lds128(a + 4 * ROWB), m1 = lds128(a + 4 * ROWB + 128), v = lds128(a + 4 * ROWB + 256);
                    b0 = lds16(ccf + (stage + 1) * 64) << psh; b1 = lds16(ccf + (stage + 1) * 64 + 32) << psh;
                    asm volatile("ld.shared.u8 %0, [%1];" : "=r"(fc) : "r"(cfl + stage + 1));
                    uint32_t u[4], z[4];
                    decode4(l0.x, l0.y, w.x, u, k28); decode4(m0.x, m0.y, v.x, z, k28);
                    issue(stage);
                    meta(stage);
                    packed_mma(l0, l1, w, m0, m1, v, u, z, c0, c1);
                } else {
                    uint4 v[4];
#pragma unroll
                    for (int r = 0; r < 4; r++) v[r] = lds128(ldr + stage * STEPB + r * 128);
                    b0 = lds16(ccf + (stage + 1) * 64) << psh; b1 = lds16(ccf + (stage + 1) * 64 + 32) << psh;
                    asm volatile("ld.shared.u8 %0, [%1];" : "=r"(fc) : "r"(cfl + stage + 1));
#pragma unroll
                    for (int r = 0; r < 4; r++) { mma8(acc[r][0], v[r].x, v[r].y, c0); mma8(acc[r][1], v[r].z, v[r].w, c0); }
                    issue(stage);
                    meta(stage);
                }
            };
            if (p0 < pend) {
                take_slot();
                goto top0;
            slow0:
                slow_body(0);
                goto back0;
            slow1:
                slow_body(1);
                goto back1;
            done0:
                finalize(node, node + 1 < nhi); node++;
                if (node == nhi) goto range_done;
                goto top1;
            done1:
                finalize(node, node + 1 < nhi); node++;
                if (node == nhi) goto range_done;
            top0:
                asm volatile("cp.async.wait_group 1;" ::: "memory");
                __syncwarp();
                mcur = mode;
                if (mcur & 1) goto slow0;
                fast_body(0);
            back0:
                mode = NEXT_MODE();
                if (mcur & 2) goto done0;
            top1:
                asm volatile("cp.async.wait_group 1;" ::: "memory");
                __syncwarp();
                mcur = mode;
                if (mcur & 1) goto slow1;
                fast_body(1);
            back1:
                mode = NEXT_MODE();
                psrc += 32; left -= 2; ccf += 128; cfl += 2;
                if (mcur & 2) goto done1;
                goto top0;
            range_done:;
            }
            asm volatile("cp.async.wait_group 0;" ::: "memory");
        } else {
            for (int node = warp; node < nn; node += NGW) { take_slot(); generic_node(node); finalize(node, false); }
        }
        TMW(1, 4 + warp);
    } else {
        const int w = warp - NGW;
        const int g = lane >> 2, t = lane & 3;
        auto tiles = [&](const int t0, const int t1) {
            uint4 wf[20];
#pragma unroll
            for (int ks = 0; ks < 20; ks++) wf[ks] = __ldcg(&g_wfrag[(ks * 4 + w) * 32 + lane]);
            for (int tile = t0; tile < t1; tile++) {
                mbar_wait(bar0 + (BAR_FULL + tile) * 8, 0);
            const uint32_t pa = smem_u32(smem + OFF_P + (tile % NBUF) * PTILE) + (lane & 15) * PNODE + (lane >> 4) * 16;
            float o0[2][4], o1[3][2][4];
#pragma unroll
            for (int j = 0; j < 2; j++)
#pragma unroll
                for (int i = 0; i < 4; i++) { o0[j][i] = 0.f; o1[0][j][i] = 0.f; o1[1][j][i] = 0.f; o1[2][j][i] = 0.f; }
#pragma unroll
            for (int ks = 0; ks < 8; ks++) {
                uint32_t a0, a1, a2, a3;
                asm volatile("ldmatrix.sync.aligned.m8n8.x4.shared.b16 {%0,%1,%2,%3}, [%4];" : "=r"(a0), "=r"(a1), "=r"(a2), "=r"(a3) : "r"(pa + (ks >> 2) * PCOMB + (ks & 3) * 32));
                const uint4 bw = wf[ks];
                mma16(o0[0], a0, a1, a2, a3, bw.x, bw.y);
                mma16(o0[1], a0, a1, a2, a3, bw.z, bw.w);
            }
#pragma unroll
            for (int ks = 0; ks < 12; ks++) {
                const uint4 bw = wf[8 + ks];
#pragma unroll
                for (int j = 0; j < 3; j++) {
                    uint32_t a0, a1, a2, a3;
                    asm volatile("ldmatrix.sync.aligned.m8n8.x4.shared.b16 {%0,%1,%2,%3}, [%4];" : "=r"(a0), "=r"(a1), "=r"(a2), "=r"(a3) : "r"(pa + (2 + j + 3 * (ks >> 2)) * PCOMB + (ks & 3) * 32));
                    mma16(o1[j][0], a0, a1, a2, a3, bw.x, bw.y);
                    mma16(o1[j][1], a0, a1, a2, a3, bw.z, bw.w);
                }
            }
            __syncwarp();
            if (lane == 0) mbar_arrive(bar0 + (BAR_FREE + tile) * 8);
#pragma unroll
            for (int hh = 0; hh < 2; hh++) {
                const int slot = tile * 16 + g + 8 * hh;
                if (slot < nn) {
                    const int node = tnode[slot];
                    const float a[4] = {o0[0][2 * hh], o0[0][2 * hh + 1], o0[1][2 * hh], o0[1][2 * hh + 1]};
                    float gt[4];
#pragma unroll
                    for (int i = 0; i < 4; i++) { float r; asm("rcp.approx.f32 %0, %1;" : "=f"(r) : "f"(1.f + __expf(-a[i]))); gt[i] = r; }
                    __nv_bfloat16* op = out + (size_t)(nstart + node) * 256 + 16 * w + 4 * t;
                    *reinterpret_cast<uint2*>(op) = make_uint2(pack_bf(a[0], a[1]), pack_bf(a[2], a[3]));
#pragma unroll
                    for (int j = 0; j < 3; j++)
                        *reinterpret_cast<uint2*>(op + 64 * (j + 1)) =
                            make_uint2(pack_bf(o1[j][0][2 * hh] * gt[0], o1[j][0][2 * hh + 1] * gt[1]), pack_bf(o1[j][1][2 * hh] * gt[2], o1[j][1][2 * hh + 1] * gt[3]));
                }
            }
            }
        };
        tiles(0, ntiles);
        TMW(1, 4 + warp);
    }
}

}

extern "C" void kernel_launch(void* const* d_in, const int* in_sizes, int n_in, void* d_out, int out_size) {
    (void)in_sizes; (void)n_in; (void)out_size;
    static bool init = false;
    if (!init) {
        cudaFuncSetAttribute(fused_kernel, cudaFuncAttributeMaxDynamicSharedMemorySize, SMEM_BYTES);
        init = true;
    }
    cudaLaunchConfig_t cfg = {};
    cfg.gridDim = dim3(NBINS); cfg.blockDim = dim3(NT); cfg.dynamicSmemBytes = SMEM_BYTES; cfg.stream = cudaStreamPerThread;
    cudaLaunchAttribute attr[1];
    attr[0].id = cudaLaunchAttributeCooperative;
    attr[0].val.cooperative = 1;
    cfg.attrs = attr; cfg.numAttrs = 1;
    cudaLaunchKernelEx(&cfg, fused_kernel,
        (const uint4*)d_in[0], (const __nv_bfloat16*)d_in[1], (const __nv_bfloat16*)d_in[2], (const int*)d_in[3], (const int*)d_in[4],
        (const __nv_bfloat16*)d_in[5], (const __nv_bfloat16*)d_in[6], (const __nv_bfloat16*)d_in[7], (const __nv_bfloat16*)d_in[8],
        (__nv_bfloat16*)d_out);
}
```
